```python
import torch

def _softmax(x, axis=-1):
    return torch.softmax(x, dim=axis)
def _gelu(x):
    return torch.nn.functional.gelu(x, approximate="tanh")
def _silu(x):
    return torch.nn.functional.silu(x)
def _sigmoid(x):
    return torch.sigmoid(x)
def _layernorm(x, axis=-1, eps=1e-5):
    m = x.mean(dim=axis, keepdim=True)
    v = x.var(dim=axis, keepdim=True, unbiased=False)
    return (x - m) / torch.sqrt(v + eps)
def _scatter_add(tgt, idx, src, axis=0):
    return tgt.clone().index_add_(axis, idx, src)
def _segment_sum(src, seg, n):
    out = torch.zeros((n,) + src.shape[1:], dtype=src.dtype)
    return out.index_add_(0, seg, src)
def _pad(x, pw):
    flat = tuple(v for pair in reversed(pw) for v in pair)
    return torch.nn.functional.pad(x, flat)

kernel_name = 'gated_mix__ssm_conv_s4__linear_attn_block__prompt'

def setup_inputs():

    _w = (lambda a: (lambda t: t.to(torch.bfloat16) if t.is_floating_point() else t)(torch.as_tensor(a)))
    def _A_setup():
        B, L, D, N = 1, 2048, 640, 128
        A_re = -(lambda _x: torch.exp(torch.as_tensor(_x)))((lambda *s: torch.randn(*s, dtype=torch.bfloat16) * 3.2)(D, N))
        A_im = torch.pi * (lambda *s: torch.randn(*s, dtype=torch.bfloat16) * 0.05)(D, N)
        B_re = (lambda *s: torch.randn(*s, dtype=torch.bfloat16) * 0.2)(D, N)
        B_im = (lambda *s: torch.randn(*s, dtype=torch.bfloat16) * 0.2)(D, N)
        C_re = (lambda *s: torch.randn(*s, dtype=torch.bfloat16) * 0.2)(D, N)
        C_im = (lambda *s: torch.randn(*s, dtype=torch.bfloat16) * 0.2)(D, N)
        log_dt = (lambda *s: torch.randn(*s, dtype=torch.bfloat16) * 0.05)(D) * 0.5 - 4.0
        Dskip = (lambda *s: torch.randn(*s, dtype=torch.bfloat16) * 0.05)(D)
        return {
            "u": _w((lambda *s: torch.randn(*s, dtype=torch.bfloat16) * 0.05)(B, L, D)),
            "A_re": _w(A_re),
            "A_im": _w(A_im),
            "B_re": _w(B_re),
            "B_im": _w(B_im),
            "C_re": _w(C_re),
            "C_im": _w(C_im),
            "log_dt": _w(log_dt),
            "Dskip": _w(Dskip),
        }
    _A_in = _A_setup()

    def _B_setup():
        B, S, D = 1, 2048, 640
        return {
            "x": _w((lambda *s: torch.randn(*s, dtype=torch.bfloat16) * 0.05)(B, S, D)),
            "wqkv": _w((lambda *s: torch.randn(*s, dtype=torch.bfloat16) * 0.8)(D, 3 * D)),
            "wo": _w((lambda *s: torch.randn(*s, dtype=torch.bfloat16) * 0.05)(D, D)),
        }
    _B_in = _B_setup()

    return {
        "A_u": _A_in["u"],
        "A_A_re": _A_in["A_re"],
        "A_A_im": _A_in["A_im"],
        "A_B_re": _A_in["B_re"],
        "A_B_im": _A_in["B_im"],
        "A_C_re": _A_in["C_re"],
        "A_C_im": _A_in["C_im"],
        "A_log_dt": _A_in["log_dt"],
        "A_Dskip": _A_in["Dskip"],
        "B_x": _B_in["x"],
        "B_wqkv": _B_in["wqkv"],
        "B_wo": _B_in["wo"],
        "gate_w": _w((lambda *s: torch.randn(*s, dtype=torch.bfloat16) * 0.05)(640) * 16.0),
    }

def reference(A_u, A_A_re, A_A_im, A_B_re, A_B_im, A_C_re, A_C_im, A_log_dt, A_Dskip, B_x, B_wqkv, B_wo, gate_w):
    def _A_ref(u, A_re, A_im, B_re, B_im, C_re, C_im, log_dt, Dskip):
        Bsz, L, D = u.shape
        dt = torch.exp(log_dt)[:, None]
        A = A_re + 1j * A_im
        Bc = B_re + 1j * B_im
        Cc = C_re + 1j * C_im
        logdA = dt * A
        dB = dt * Bc
        l = (lambda x, dt: x.to(dt))(torch.arange(L), A_re.dtype)
        P = torch.exp(logdA[:, :, None] * l[None, None, :])
        K = torch.einsum("dn,dnl,dn->dl", Cc, P, dB).real
        L2 = 2 * L
        Kp = _pad(K, ((0, 0), (0, L)))
        up = (lambda x, *d: x.permute(*d))(u, 0, 2, 1)
        up = _pad(up, ((0, 0), (0, 0), (0, L)))
        Kf = (lambda x, axes=(-2,-1): torch.fft.rfft2(x.float(), dim=axes))(Kp[:, None, :], axes=(-2, -1))
        Uf = (lambda x, axes=(-2,-1): torch.fft.rfft2(x.float(), dim=axes))(up[:, :, None, :], axes=(-2, -1))
        Yf = Uf * Kf[None, :, :, :]
        y = (lambda x, s, axes=(-2,-1): torch.fft.irfft2(x, s=s, dim=axes).to(torch.bfloat16))(Yf, (1, L2), axes=(-2, -1))[:, :, 0, :L]
        y = (lambda x, *d: x.permute(*d))(y, 0, 2, 1) + u * Dskip[None, None, :]
        return y

    def _B_ref(x, wqkv, wo):
        B, S, D = x.shape
        H = 32; Dh = D // H
        qkv = (lambda x, *d: x.permute(*d))((x @ wqkv).reshape(B, S, 3, H, Dh), 2, 0, 3, 1, 4)
        q, k, v = qkv[0], qkv[1], qkv[2]
        phi = lambda t: torch.where(t > 0, t + 1, torch.exp(t)) + 1e-6
        pq, pk = phi(q), phi(k)
        kv = torch.einsum("bhsd,bhse->bhde", pk, v)
        z = torch.einsum("bhsd->bhd", pk)
        num = torch.einsum("bhqd,bhde->bhqe", pq, kv)
        den = torch.einsum("bhqd,bhd->bhq", pq, z)[..., None] + 1e-6
        o = num / den
        return (lambda x, *d: x.permute(*d))(o, 0, 2, 1, 3).reshape(B, S, D) @ wo

    x = A_u
    g = _sigmoid((x * gate_w).sum(-1, keepdims=True))
    a = _A_ref(x, A_A_re, A_A_im, A_B_re, A_B_im, A_C_re, A_C_im, A_log_dt, A_Dskip)
    b = _B_ref(x, B_wqkv, B_wo)
    return g * a + (1 - g) * b
```

```cpp
#include <cuda_runtime.h>
#include <cuda.h>
#include <cuda_bf16.h>
#include <stdint.h>

#define SPIN_LIMIT (1 << 22)

namespace gm {

#define G1BV 2
constexpr int G1B = G1BV;
constexpr int NST = 3;
constexpr uint32_t STG = 47104;
constexpr uint32_t OFF_XS = 141312;
constexpr uint32_t BMP = 400;
constexpr uint32_t KTB = 32 * BMP + 2048;
constexpr uint32_t OFF_KT = 172032;
constexpr uint32_t KCB = 1312;
constexpr uint32_t OFF_KC = OFF_KT + KTB;
constexpr uint32_t OFF_GW = OFF_KC + 5 * KCB;
constexpr uint32_t OFF_PK = 0;
constexpr uint32_t OFF_V = OFF_PK + 26624;
constexpr uint32_t OFF_WO = 53248;
constexpr uint32_t OFF_BT = 155648;
constexpr uint32_t OFF_OST = OFF_PK;
constexpr uint32_t OFF_OUT = 0;
__device__ __forceinline__ uint32_t oring(int s) { return s == 3 ? 155648u : (uint32_t)s * 16384u; }
constexpr uint32_t OFF_AT = OFF_KT;
constexpr uint32_t OFF_SSM = 198656;
constexpr uint32_t OFF_XT0 = OFF_XS + 20480;
constexpr uint32_t OFF_XT1 = OFF_SSM + 9216;
constexpr uint32_t OFF_P = OFF_SSM;
constexpr uint32_t OFF_YST = OFF_SSM + 16640;
constexpr uint32_t OFF_UT = OFF_SSM + 20736;
constexpr uint32_t OFF_GP = OFF_SSM + 30976;
constexpr uint32_t OFF_BAR = OFF_SSM + 31488;
constexpr uint32_t OFF_CNT = OFF_BAR + 224;
constexpr uint32_t OFF_TS = OFF_BAR + 256;
constexpr uint32_t SMEM_BYTES = OFF_TS;
constexpr uint32_t UPL = 2560;

enum { B_FULL = 0, B_WO = 3, B_OFULL = 4, B_OEMPTY = 8, B_AT = 12, B_XS = 13, B_UT = 14, B_PFULL = 16, B_PEMPTY = 18, B_XD = 20, B_P2 = 21, B_KC = 22, B_N = 25 };

__device__ __align__(1024) __nv_bfloat16 g_uT[640 * 2048];
__device__ __align__(1024) __nv_bfloat16 g_aT[640 * 2048];
__device__ __align__(1024) __nv_bfloat16 g_o[2048 * 640];
__device__ __align__(1024) float g_kv[2][32 * 20 * 24];
__device__ __align__(1024) float g_gp[16 * 8 * 128];
__device__ __align__(1024) unsigned g_cnt[40 * 32];
__device__ unsigned g_epoch;
#define TSTAMP(i) do {} while (0)

__device__ __forceinline__ uint32_t smem_u32(const void* p) { return (uint32_t)__cvta_generic_to_shared(p); }
__device__ __forceinline__ void mbar_init(uint32_t bar, uint32_t cnt) { asm volatile("mbarrier.init.shared::cta.b64 [%0], %1;" ::"r"(bar), "r"(cnt)); }
__device__ __forceinline__ void mbar_expect_tx(uint32_t bar, uint32_t bytes) { asm volatile("mbarrier.arrive.expect_tx.shared::cta.b64 _, [%0], %1;" ::"r"(bar), "r"(bytes) : "memory"); }
__device__ __forceinline__ void mbar_arrive(uint32_t bar) { asm volatile("mbarrier.arrive.shared::cta.b64 _, [%0];" ::"r"(bar) : "memory"); }
__device__ __forceinline__ void mbar_wait(uint32_t bar, uint32_t parity) {
  uint32_t ok; int n = 0;
  while (true) {
    asm volatile("{ .reg .pred p; mbarrier.try_wait.parity.shared::cta.b64 p, [%1], %2; selp.u32 %0,1,0,p; }" : "=r"(ok) : "r"(bar), "r"(parity) : "memory");
    if (ok || ++n >= (1 << 16)) break;
    __nanosleep(64);
  }
}
__device__ __forceinline__ bool mbar_test(uint32_t bar, uint32_t parity) {
  uint32_t ok;
  asm volatile("{ .reg .pred p; mbarrier.test_wait.parity.shared::cta.b64 p, [%1], %2; selp.u32 %0,1,0,p; }" : "=r"(ok) : "r"(bar), "r"(parity) : "memory");
  return ok != 0;
}
__device__ __forceinline__ void poll_ge(const unsigned* p, unsigned target) {
  unsigned v; int n = 0;
  do { asm volatile("ld.relaxed.gpu.global.u32 %0, [%1];" : "=r"(v) : "l"(p) : "memory"); } while ((int)(v - target) < 0 && ++n < SPIN_LIMIT);
  asm volatile("ld.acquire.gpu.global.u32 %0, [%1];" : "=r"(v) : "l"(p) : "memory");
}
__device__ __forceinline__ void mbar_arrive_n(uint32_t bar, uint32_t n) { asm volatile("mbarrier.arrive.shared::cta.b64 _, [%0], %1;" ::"r"(bar), "r"(n) : "memory"); }
__device__ __forceinline__ uint32_t atom_inc_smem(uint32_t a) { uint32_t o; asm volatile("atom.acq_rel.cta.shared::cta.add.u32 %0, [%1], 1;" : "=r"(o) : "r"(a) : "memory"); return o; }
__device__ __forceinline__ void red_release(unsigned* p) { asm volatile("red.release.gpu.global.add.u32 [%0], 1;" ::"l"(p) : "memory"); }
__device__ __forceinline__ void red_relaxed(unsigned* p) { asm volatile("red.relaxed.gpu.global.add.u32 [%0], 1;" ::"l"(p) : "memory"); }
__device__ __forceinline__ void fence_async() { asm volatile("fence.proxy.async.shared::cta;" ::: "memory"); }
__device__ __forceinline__ void fence_async_g() { asm volatile("fence.proxy.async.global;" ::: "memory"); }
__device__ __forceinline__ void bar_sync(int id, int n) { asm volatile("bar.sync %0, %1;" ::"r"(id), "r"(n) : "memory"); }
__device__ __forceinline__ bool elect() {
  uint32_t l; asm volatile("{ .reg .pred p; elect.sync _|p, 0xffffffff; selp.u32 %0,1,0,p; }" : "=r"(l)); return l != 0;
}
__device__ __forceinline__ void tma2d(uint32_t dst, const CUtensorMap* tm, int c0, int c1, uint32_t bar) {
  asm volatile("cp.async.bulk.tensor.2d.shared::cluster.global.mbarrier::complete_tx::bytes [%0], [%1, {%3,%4}], [%2];"
               ::"r"(dst), "l"(tm), "r"(bar), "r"(c0), "r"(c1) : "memory");
}
__device__ __forceinline__ void tma3d(uint32_t dst, const CUtensorMap* tm, int c0, int c1, int c2, uint32_t bar) {
  asm volatile("cp.async.bulk.tensor.3d.shared::cluster.global.mbarrier::complete_tx::bytes [%0], [%1, {%3,%4,%5}], [%2];"
               ::"r"(dst), "l"(tm), "r"(bar), "r"(c0), "r"(c1), "r"(c2) : "memory");
}
__device__ __forceinline__ void tma2d_store(const CUtensorMap* tm, uint32_t src, int c0, int c1) {
  asm volatile("cp.async.bulk.tensor.2d.global.shared::cta.bulk_group [%0, {%2,%3}], [%1];" ::"l"(tm), "r"(src), "r"(c0), "r"(c1) : "memory");
}
__device__ __forceinline__ void tma4d(uint32_t dst, const CUtensorMap* tm, int c0, int c1, int c2, int c3, uint32_t bar) {
  asm volatile("cp.async.bulk.tensor.4d.shared::cluster.global.mbarrier::complete_tx::bytes [%0], [%1, {%3,%4,%5,%6}], [%2];"
               ::"r"(dst), "l"(tm), "r"(bar), "r"(c0), "r"(c1), "r"(c2), "r"(c3) : "memory");
}
__device__ __forceinline__ void prefetch_tm(const CUtensorMap* tm) { asm volatile("prefetch.tensormap [%0];" ::"l"(tm) : "memory"); }
__device__ __forceinline__ void bulk_load(uint32_t dst, const void* src, uint32_t bytes, uint32_t bar) {
  asm volatile("cp.async.bulk.shared::cluster.global.mbarrier::complete_tx::bytes [%0], [%1], %2, [%3];" ::"r"(dst), "l"(src), "r"(bytes), "r"(bar) : "memory");
}
__device__ __forceinline__ void bulk_store(void* dst, uint32_t src, uint32_t bytes) {
  asm volatile("cp.async.bulk.global.shared::cta.bulk_group [%0], [%1], %2;" ::"l"(dst), "r"(src), "r"(bytes) : "memory");
}
__device__ __forceinline__ void bulk_reduce_f32(void* dst, uint32_t src, uint32_t bytes) {
  asm volatile("cp.reduce.async.bulk.global.shared::cta.bulk_group.add.f32 [%0], [%1], %2;" ::"l"(dst), "r"(src), "r"(bytes) : "memory");
}
__device__ __forceinline__ void bulk_commit() { asm volatile("cp.async.bulk.commit_group;" ::: "memory"); }
__device__ __forceinline__ void bulk_wait_all() { asm volatile("cp.async.bulk.wait_group 0;" ::: "memory"); }
__device__ __forceinline__ void bulk_wait_read() { asm volatile("cp.async.bulk.wait_group.read 0;" ::: "memory"); }
__device__ __forceinline__ uint64_t mkdesc(uint32_t saddr, uint32_t lbo, uint32_t sbo, uint32_t layout) {
  uint64_t d = 0;
  d |= (uint64_t)((saddr >> 4) & 0x3FFF); d |= (uint64_t)((lbo >> 4) & 0x3FFF) << 16; d |= (uint64_t)((sbo >> 4) & 0x3FFF) << 32; d |= (uint64_t)layout << 62;
  return d;
}
__device__ __forceinline__ uint32_t desc_lo(uint32_t saddr, uint32_t lbo) { return ((saddr >> 4) & 0x3FFF) | ((lbo >> 4) << 16); }
__device__ __forceinline__ uint64_t desc_mk(uint32_t lo, uint32_t sbo, uint32_t layout) { return ((uint64_t)((sbo >> 4) | (layout << 30)) << 32) | lo; }
__device__ __forceinline__ void ldsm4(uint32_t a, uint32_t& r0, uint32_t& r1, uint32_t& r2, uint32_t& r3) {
  asm volatile("ldmatrix.sync.aligned.m8n8.x4.shared.b16 {%0,%1,%2,%3}, [%4];" : "=r"(r0), "=r"(r1), "=r"(r2), "=r"(r3) : "r"(a) : "memory");
}
__device__ __forceinline__ void ldsm2(uint32_t a, uint32_t& r0, uint32_t& r1) {
  asm volatile("ldmatrix.sync.aligned.m8n8.x2.shared.b16 {%0,%1}, [%2];" : "=r"(r0), "=r"(r1) : "r"(a) : "memory");
}
__device__ __forceinline__ void wg_fence() { asm volatile("wgmma.fence.sync.aligned;" ::: "memory"); }
__device__ __forceinline__ void wg_commit() { asm volatile("wgmma.commit_group.sync.aligned;" ::: "memory"); }
template <int N> __device__ __forceinline__ void wg_wait() { asm volatile("wgmma.wait_group.sync.aligned %0;" ::"n"(N) : "memory"); }
__device__ __forceinline__ uint32_t pack2(float lo, float hi) { uint32_t r; asm("cvt.rn.bf16x2.f32 %0, %1, %2;" : "=r"(r) : "f"(hi), "f"(lo)); return r; }
__device__ __forceinline__ float bf_lo(uint32_t v) { return __uint_as_float(v << 16); }
__device__ __forceinline__ float bf_hi(uint32_t v) { return __uint_as_float(v & 0xffff0000u); }
__device__ __forceinline__ float bfr(float x) { return __bfloat162float(__float2bfloat16_rn(x)); }
__device__ __forceinline__ float ex2f(float x) { float r; asm("ex2.approx.ftz.f32 %0, %1;" : "=f"(r) : "f"(x)); return r; }
__device__ __forceinline__ uint32_t lds32(uint32_t a) { uint32_t v; asm volatile("ld.shared.u32 %0, [%1];" : "=r"(v) : "r"(a) : "memory"); return v; }
__device__ __forceinline__ float lds32f(uint32_t a) { float v; asm volatile("ld.shared.f32 %0, [%1];" : "=f"(v) : "r"(a) : "memory"); return v; }
__device__ __forceinline__ uint32_t lds16(uint32_t a) { uint16_t v; asm volatile("ld.shared.u16 %0, [%1];" : "=h"(v) : "r"(a) : "memory"); return v; }
__device__ __forceinline__ float2 lds64f(uint32_t a) { float2 v; asm volatile("ld.shared.v2.f32 {%0,%1}, [%2];" : "=f"(v.x), "=f"(v.y) : "r"(a) : "memory"); return v; }
__device__ __forceinline__ void sts32(uint32_t a, uint32_t v) { asm volatile("st.shared.u32 [%0], %1;" ::"r"(a), "r"(v) : "memory"); }
__device__ __forceinline__ void sts32f(uint32_t a, float v) { asm volatile("st.shared.f32 [%0], %1;" ::"r"(a), "f"(v) : "memory"); }
__device__ __forceinline__ void sts16(uint32_t a, uint32_t v) { asm volatile("st.shared.u16 [%0], %1;" ::"r"(a), "h"((uint16_t)v) : "memory"); }
__device__ __forceinline__ void sts64f(uint32_t a, float x, float y) { asm volatile("st.shared.v2.f32 [%0], {%1,%2};" ::"r"(a), "f"(x), "f"(y) : "memory"); }
__device__ __forceinline__ void sts64(uint32_t a, uint32_t x, uint32_t y) { asm volatile("st.shared.v2.u32 [%0], {%1,%2};" ::"r"(a), "r"(x), "r"(y) : "memory"); }
__device__ __forceinline__ void sts128(uint32_t a, uint32_t x, uint32_t y, uint32_t z, uint32_t w) {
  asm volatile("st.shared.v4.u32 [%0], {%1,%2,%3,%4};" ::"r"(a), "r"(x), "r"(y), "r"(z), "r"(w) : "memory");
}
__device__ __forceinline__ uint4 lds128(uint32_t a) {
  uint4 v; asm volatile("ld.shared.v4.u32 {%0,%1,%2,%3}, [%4];" : "=r"(v.x), "=r"(v.y), "=r"(v.z), "=r"(v.w) : "r"(a) : "memory"); return v;
}
__device__ __forceinline__ void ldsm4t(uint32_t a, uint32_t& r0, uint32_t& r1, uint32_t& r2, uint32_t& r3) {
  asm volatile("ldmatrix.sync.aligned.m8n8.x4.trans.shared.b16 {%0,%1,%2,%3}, [%4];" : "=r"(r0), "=r"(r1), "=r"(r2), "=r"(r3) : "r"(a) : "memory");
}
__device__ __forceinline__ void ldsm2t(uint32_t a, uint32_t& r0, uint32_t& r1) {
  asm volatile("ldmatrix.sync.aligned.m8n8.x2.trans.shared.b16 {%0,%1}, [%2];" : "=r"(r0), "=r"(r1) : "r"(a) : "memory");
}
__device__ __forceinline__ void stsm4t(uint32_t a, uint32_t r0, uint32_t r1, uint32_t r2, uint32_t r3) {
  asm volatile("stmatrix.sync.aligned.m8n8.x4.trans.shared.b16 [%0], {%1,%2,%3,%4};" ::"r"(a), "r"(r0), "r"(r1), "r"(r2), "r"(r3) : "memory");
}
__device__ __forceinline__ void stsm1t(uint32_t a, uint32_t r0) {
  asm volatile("stmatrix.sync.aligned.m8n8.x1.trans.shared.b16 [%0], {%1};" ::"r"(a), "r"(r0) : "memory");
}
__device__ __forceinline__ void stsm4(uint32_t a, uint32_t r0, uint32_t r1, uint32_t r2, uint32_t r3) {
  asm volatile("stmatrix.sync.aligned.m8n8.x4.shared.b16 [%0], {%1,%2,%3,%4};" ::"r"(a), "r"(r0), "r"(r1), "r"(r2), "r"(r3) : "memory");
}
__device__ __forceinline__ void mma16816(float* c, uint32_t a0, uint32_t a1, uint32_t a2, uint32_t a3, uint32_t b0, uint32_t b1) {
  asm volatile("mma.sync.aligned.m16n8k16.row.col.f32.bf16.bf16.f32 {%0,%1,%2,%3}, {%4,%5,%6,%7}, {%8,%9}, {%0,%1,%2,%3};"
               : "+f"(c[0]), "+f"(c[1]), "+f"(c[2]), "+f"(c[3]) : "r"(a0), "r"(a1), "r"(a2), "r"(a3), "r"(b0), "r"(b1));
}
__device__ __forceinline__ uint32_t hmul2rn(uint32_t a, uint32_t b) { uint32_t r; asm("mul.rn.bf16x2 %0, %1, %2;" : "=r"(r) : "r"(a), "r"(b)); return r; }
__device__ __forceinline__ uint32_t hadd2rn(uint32_t a, uint32_t b) { uint32_t r; asm("add.rn.bf16x2 %0, %1, %2;" : "=r"(r) : "r"(a), "r"(b)); return r; }

__device__ __forceinline__ uint32_t phi2(float a, float b) {
  uint32_t t = pack2(a, b);
  float ta = bf_lo(t), tb = bf_hi(t);
  float ea = ex2f(ta * 1.4426950408889634f), eb = ex2f(tb * 1.4426950408889634f);
  float pa = ta > 0.f ? ta + 1.f : ea, pb = tb > 0.f ? tb + 1.f : eb;
  uint32_t p = pack2(pa, pb);
  return pack2(bf_lo(p) + 1e-6f, bf_hi(p) + 1e-6f);
}

template <int N> __device__ __forceinline__ void wgmma_rs(float* d, uint32_t a0, uint32_t a1, uint32_t a2, uint32_t a3, uint64_t db, int sc);
template<> __device__ __forceinline__ void wgmma_rs<16>(float* d, uint32_t a0, uint32_t a1, uint32_t a2, uint32_t a3, uint64_t db, int sc){
  asm volatile("{ .reg .pred p; setp.ne.b32 p, %13, 0;\n"
  "wgmma.mma_async.sync.aligned.m64n16k16.f32.bf16.bf16 {%0,%1,%2,%3,%4,%5,%6,%7}, {%8,%9,%10,%11}, %12, p, 1, 1, 0; }"
  : "+f"(d[0]),"+f"(d[1]),"+f"(d[2]),"+f"(d[3]),"+f"(d[4]),"+f"(d[5]),"+f"(d[6]),"+f"(d[7])
  : "r"(a0),"r"(a1),"r"(a2),"r"(a3),"l"(db),"r"(sc));
}

template<> __device__ __forceinline__ void wgmma_rs<24>(float* d, uint32_t a0, uint32_t a1, uint32_t a2, uint32_t a3, uint64_t db, int sc){
  asm volatile("{ .reg .pred p; setp.ne.b32 p, %17, 0;\n"
  "wgmma.mma_async.sync.aligned.m64n24k16.f32.bf16.bf16 {%0,%1,%2,%3,%4,%5,%6,%7,%8,%9,%10,%11}, {%12,%13,%14,%15}, %16, p, 1, 1, 0; }"
  : "+f"(d[0]),"+f"(d[1]),"+f"(d[2]),"+f"(d[3]),"+f"(d[4]),"+f"(d[5]),"+f"(d[6]),"+f"(d[7]),"+f"(d[8]),"+f"(d[9]),"+f"(d[10]),"+f"(d[11])
  : "r"(a0),"r"(a1),"r"(a2),"r"(a3),"l"(db),"r"(sc));
}

template<> __device__ __forceinline__ void wgmma_rs<32>(float* d, uint32_t a0, uint32_t a1, uint32_t a2, uint32_t a3, uint64_t db, int sc){
  asm volatile("{ .reg .pred p; setp.ne.b32 p, %21, 0;\n"
  "wgmma.mma_async.sync.aligned.m64n32k16.f32.bf16.bf16 {%0,%1,%2,%3,%4,%5,%6,%7,%8,%9,%10,%11,%12,%13,%14,%15}, {%16,%17,%18,%19}, %20, p, 1, 1, 0; }"
  : "+f"(d[0]),"+f"(d[1]),"+f"(d[2]),"+f"(d[3]),"+f"(d[4]),"+f"(d[5]),"+f"(d[6]),"+f"(d[7]),"+f"(d[8]),"+f"(d[9]),"+f"(d[10]),"+f"(d[11]),"+f"(d[12]),"+f"(d[13]),"+f"(d[14]),"+f"(d[15])
  : "r"(a0),"r"(a1),"r"(a2),"r"(a3),"l"(db),"r"(sc));
}

template<> __device__ __forceinline__ void wgmma_rs<48>(float* d, uint32_t a0, uint32_t a1, uint32_t a2, uint32_t a3, uint64_t db, int sc){
  asm volatile("{ .reg .pred p; setp.ne.b32 p, %29, 0;\n"
  "wgmma.mma_async.sync.aligned.m64n48k16.f32.bf16.bf16 {%0,%1,%2,%3,%4,%5,%6,%7,%8,%9,%10,%11,%12,%13,%14,%15,%16,%17,%18,%19,%20,%21,%22,%23}, {%24,%25,%26,%27}, %28, p, 1, 1, 0; }"
  : "+f"(d[0]),"+f"(d[1]),"+f"(d[2]),"+f"(d[3]),"+f"(d[4]),"+f"(d[5]),"+f"(d[6]),"+f"(d[7]),"+f"(d[8]),"+f"(d[9]),"+f"(d[10]),"+f"(d[11]),"+f"(d[12]),"+f"(d[13]),"+f"(d[14]),"+f"(d[15]),"+f"(d[16]),"+f"(d[17]),"+f"(d[18]),"+f"(d[19]),"+f"(d[20]),"+f"(d[21]),"+f"(d[22]),"+f"(d[23])
  : "r"(a0),"r"(a1),"r"(a2),"r"(a3),"l"(db),"r"(sc));
}

template<> __device__ __forceinline__ void wgmma_rs<64>(float* d, uint32_t a0, uint32_t a1, uint32_t a2, uint32_t a3, uint64_t db, int sc){
  asm volatile("{ .reg .pred p; setp.ne.b32 p, %37, 0;\n"
  "wgmma.mma_async.sync.aligned.m64n64k16.f32.bf16.bf16 {%0,%1,%2,%3,%4,%5,%6,%7,%8,%9,%10,%11,%12,%13,%14,%15,%16,%17,%18,%19,%20,%21,%22,%23,%24,%25,%26,%27,%28,%29,%30,%31}, {%32,%33,%34,%35}, %36, p, 1, 1, 0; }"
  : "+f"(d[0]),"+f"(d[1]),"+f"(d[2]),"+f"(d[3]),"+f"(d[4]),"+f"(d[5]),"+f"(d[6]),"+f"(d[7]),"+f"(d[8]),"+f"(d[9]),"+f"(d[10]),"+f"(d[11]),"+f"(d[12]),"+f"(d[13]),"+f"(d[14]),"+f"(d[15]),"+f"(d[16]),"+f"(d[17]),"+f"(d[18]),"+f"(d[19]),"+f"(d[20]),"+f"(d[21]),"+f"(d[22]),"+f"(d[23]),"+f"(d[24]),"+f"(d[25]),"+f"(d[26]),"+f"(d[27]),"+f"(d[28]),"+f"(d[29]),"+f"(d[30]),"+f"(d[31])
  : "r"(a0),"r"(a1),"r"(a2),"r"(a3),"l"(db),"r"(sc));
}

template<> __device__ __forceinline__ void wgmma_rs<88>(float* d, uint32_t a0, uint32_t a1, uint32_t a2, uint32_t a3, uint64_t db, int sc){
  asm volatile("{ .reg .pred p; setp.ne.b32 p, %49, 0;\n"
  "wgmma.mma_async.sync.aligned.m64n88k16.f32.bf16.bf16 {%0,%1,%2,%3,%4,%5,%6,%7,%8,%9,%10,%11,%12,%13,%14,%15,%16,%17,%18,%19,%20,%21,%22,%23,%24,%25,%26,%27,%28,%29,%30,%31,%32,%33,%34,%35,%36,%37,%38,%39,%40,%41,%42,%43}, {%44,%45,%46,%47}, %48, p, 1, 1, 0; }"
  : "+f"(d[0]),"+f"(d[1]),"+f"(d[2]),"+f"(d[3]),"+f"(d[4]),"+f"(d[5]),"+f"(d[6]),"+f"(d[7]),"+f"(d[8]),"+f"(d[9]),"+f"(d[10]),"+f"(d[11]),"+f"(d[12]),"+f"(d[13]),"+f"(d[14]),"+f"(d[15]),"+f"(d[16]),"+f"(d[17]),"+f"(d[18]),"+f"(d[19]),"+f"(d[20]),"+f"(d[21]),"+f"(d[22]),"+f"(d[23]),"+f"(d[24]),"+f"(d[25]),"+f"(d[26]),"+f"(d[27]),"+f"(d[28]),"+f"(d[29]),"+f"(d[30]),"+f"(d[31]),"+f"(d[32]),"+f"(d[33]),"+f"(d[34]),"+f"(d[35]),"+f"(d[36]),"+f"(d[37]),"+f"(d[38]),"+f"(d[39]),"+f"(d[40]),"+f"(d[41]),"+f"(d[42]),"+f"(d[43])
  : "r"(a0),"r"(a1),"r"(a2),"r"(a3),"l"(db),"r"(sc));
}

__device__ __forceinline__ void wgmma_g1a(float* d, uint64_t da, uint64_t db, int sc){
  asm volatile("{ .reg .pred p; setp.ne.b32 p, %98, 0;\n"
  "wgmma.mma_async.sync.aligned.m64n192k16.f32.bf16.bf16 {%0,%1,%2,%3,%4,%5,%6,%7,%8,%9,%10,%11,%12,%13,%14,%15,%16,%17,%18,%19,%20,%21,%22,%23,%24,%25,%26,%27,%28,%29,%30,%31,%32,%33,%34,%35,%36,%37,%38,%39,%40,%41,%42,%43,%44,%45,%46,%47,%48,%49,%50,%51,%52,%53,%54,%55,%56,%57,%58,%59,%60,%61,%62,%63,%64,%65,%66,%67,%68,%69,%70,%71,%72,%73,%74,%75,%76,%77,%78,%79,%80,%81,%82,%83,%84,%85,%86,%87,%88,%89,%90,%91,%92,%93,%94,%95}, %96, %97, p, 1, 1, 0, 1; }"
  : "+f"(d[0]),"+f"(d[1]),"+f"(d[2]),"+f"(d[3]),"+f"(d[4]),"+f"(d[5]),"+f"(d[6]),"+f"(d[7]),"+f"(d[8]),"+f"(d[9]),"+f"(d[10]),"+f"(d[11]),"+f"(d[12]),"+f"(d[13]),"+f"(d[14]),"+f"(d[15]),"+f"(d[16]),"+f"(d[17]),"+f"(d[18]),"+f"(d[19]),"+f"(d[20]),"+f"(d[21]),"+f"(d[22]),"+f"(d[23]),"+f"(d[24]),"+f"(d[25]),"+f"(d[26]),"+f"(d[27]),"+f"(d[28]),"+f"(d[29]),"+f"(d[30]),"+f"(d[31]),"+f"(d[40]),"+f"(d[41]),"+f"(d[42]),"+f"(d[43]),"+f"(d[44]),"+f"(d[45]),"+f"(d[46]),"+f"(d[47]),"+f"(d[48]),"+f"(d[49]),"+f"(d[50]),"+f"(d[51]),"+f"(d[52]),"+f"(d[53]),"+f"(d[54]),"+f"(d[55]),"+f"(d[56]),"+f"(d[57]),"+f"(d[58]),"+f"(d[59]),"+f"(d[60]),"+f"(d[61]),"+f"(d[62]),"+f"(d[63]),"+f"(d[64]),"+f"(d[65]),"+f"(d[66]),"+f"(d[67]),"+f"(d[68]),"+f"(d[69]),"+f"(d[70]),"+f"(d[71]),"+f"(d[80]),"+f"(d[81]),"+f"(d[82]),"+f"(d[83]),"+f"(d[84]),"+f"(d[85]),"+f"(d[86]),"+f"(d[87]),"+f"(d[88]),"+f"(d[89]),"+f"(d[90]),"+f"(d[91]),"+f"(d[92]),"+f"(d[93]),"+f"(d[94]),"+f"(d[95]),"+f"(d[96]),"+f"(d[97]),"+f"(d[98]),"+f"(d[99]),"+f"(d[100]),"+f"(d[101]),"+f"(d[102]),"+f"(d[103]),"+f"(d[104]),"+f"(d[105]),"+f"(d[106]),"+f"(d[107]),"+f"(d[108]),"+f"(d[109]),"+f"(d[110]),"+f"(d[111])
  : "l"(da),"l"(db),"r"(sc));
}

__device__ __forceinline__ void wgmma_g1b(float* d, uint64_t da, uint64_t db, int sc){
  asm volatile("{ .reg .pred p; setp.ne.b32 p, %26, 0;\n"
  "wgmma.mma_async.sync.aligned.m64n48k16.f32.bf16.bf16 {%0,%1,%2,%3,%4,%5,%6,%7,%8,%9,%10,%11,%12,%13,%14,%15,%16,%17,%18,%19,%20,%21,%22,%23}, %24, %25, p, 1, 1, 0, 1; }"
  : "+f"(d[32]),"+f"(d[33]),"+f"(d[34]),"+f"(d[35]),"+f"(d[36]),"+f"(d[37]),"+f"(d[38]),"+f"(d[39]),"+f"(d[72]),"+f"(d[73]),"+f"(d[74]),"+f"(d[75]),"+f"(d[76]),"+f"(d[77]),"+f"(d[78]),"+f"(d[79]),"+f"(d[112]),"+f"(d[113]),"+f"(d[114]),"+f"(d[115]),"+f"(d[116]),"+f"(d[117]),"+f"(d[118]),"+f"(d[119])
  : "l"(da),"l"(db),"r"(sc));
}

__device__ __forceinline__ void wgmma_g2(float* d, uint64_t da, uint64_t db, int sc){
  asm volatile("{ .reg .pred p; setp.ne.b32 p, %42, 0;\n"
  "wgmma.mma_async.sync.aligned.m64n80k16.f32.bf16.bf16 {%0,%1,%2,%3,%4,%5,%6,%7,%8,%9,%10,%11,%12,%13,%14,%15,%16,%17,%18,%19,%20,%21,%22,%23,%24,%25,%26,%27,%28,%29,%30,%31,%32,%33,%34,%35,%36,%37,%38,%39}, %40, %41, p, 1, 1, 0, 1; }"
  : "+f"(d[0]),"+f"(d[1]),"+f"(d[2]),"+f"(d[3]),"+f"(d[4]),"+f"(d[5]),"+f"(d[6]),"+f"(d[7]),"+f"(d[8]),"+f"(d[9]),"+f"(d[10]),"+f"(d[11]),"+f"(d[12]),"+f"(d[13]),"+f"(d[14]),"+f"(d[15]),"+f"(d[16]),"+f"(d[17]),"+f"(d[18]),"+f"(d[19]),"+f"(d[20]),"+f"(d[21]),"+f"(d[22]),"+f"(d[23]),"+f"(d[24]),"+f"(d[25]),"+f"(d[26]),"+f"(d[27]),"+f"(d[28]),"+f"(d[29]),"+f"(d[30]),"+f"(d[31]),"+f"(d[32]),"+f"(d[33]),"+f"(d[34]),"+f"(d[35]),"+f"(d[36]),"+f"(d[37]),"+f"(d[38]),"+f"(d[39])
  : "l"(da),"l"(db),"r"(sc));
}

struct Params {
  const __nv_bfloat16 *Are, *Aim, *Bre, *Bim, *Cre, *Cim, *logdt, *dskip, *gatew;
};
struct Raw { uint16_t are, aim, bre, bim, cre, cim, ld, ds; };
__device__ __forceinline__ uint16_t ldg16(const __nv_bfloat16* p) { uint16_t v; asm volatile("ld.global.nc.u16 %0, [%1];" : "=h"(v) : "l"(p)); return v; }
__device__ __forceinline__ float bf16f(uint16_t v) { return __uint_as_float((uint32_t)v << 16); }
__device__ __forceinline__ Raw load_raw(const Params& P, int d, int n) {
  Raw r; const int o = d * 128 + n;
  r.are = ldg16(P.Are + o); r.aim = ldg16(P.Aim + o); r.bre = ldg16(P.Bre + o); r.bim = ldg16(P.Bim + o);
  r.cre = ldg16(P.Cre + o); r.cim = ldg16(P.Cim + o); r.ld = ldg16(P.logdt + d); r.ds = ldg16(P.dskip + d);
  return r;
}
__device__ __forceinline__ void csq(float& re, float& im) { float t = im * im; float r2 = fmaf(re, re, -t); im = (re + re) * im; re = r2; }
__device__ __forceinline__ void cmul(float& re, float& im, float br, float bi) { float r2 = fmaf(re, br, -im * bi); im = fmaf(re, bi, im * br); re = r2; }
__device__ __forceinline__ void polar(float ar2, float ai, float p, float& re, float& im) {
  float e = ex2f(ar2 * p), s, c;
  __sincosf(ai * p, &s, &c);
  re = e * c; im = e * s;
}

__device__ __forceinline__ void kgen_channel(uint32_t kt, uint32_t kcb, int barid, const Params& P, Raw& raw, int dcur, int dnext, uint32_t sb, long long t_start, int ts) {
  const int tid = threadIdx.x & 127, lane = tid & 31, w = tid >> 5, g = lane >> 2, t = lane & 3;
  const uint32_t kc = kcb + 16, ap = kt + 32 * BMP;
  const float pf = (float)(8 * g);
  const int rr = tid >> 2, c6 = (tid & 3) * 6;
  if (tid < 4) sts32(kcb + tid * 4, 0);
  const float dsk = bf16f(raw.ds);
  {
    const float dt = bfr(expf(bf16f(raw.ld)));
    const float ar2 = dt * bf16f(raw.are) * 1.4426950408889634f, ai = dt * bf16f(raw.aim);
    const float br = dt * bf16f(raw.bre), bi = dt * bf16f(raw.bim);
    const float c_r = bf16f(raw.cre), c_i = bf16f(raw.cim);
    const float cr = c_r * br - c_i * bi, ci = c_r * bi + c_i * br;
    float w1r, w1i, Wr, Wi;
    polar(ar2, ai, 64.f, Wr, Wi);
    sts128(ap + tid * 16, __float_as_uint(ar2), __float_as_uint(ai), __float_as_uint(Wr), __float_as_uint(Wi));
    polar(ar2, ai, 1.f, w1r, w1i);
    polar(ar2, ai, 256.f, Wr, Wi);
    const uint32_t bm = kt + (tid >> 2) * BMP + (tid & 3) * 4;
    float zr = cr, zi = ci, yr = cr, yi = ci;
    cmul(yr, yi, Wr, Wi);
    sts32(bm, pack2(zr, -zi));
    sts32(bm + 128, pack2(yr, -yi));
    float w2r = w1r, w2i = w1i; csq(w2r, w2i);
    float xr = yr, xi = yi; cmul(xr, xi, Wr, Wi);
#pragma unroll
    for (int p = 1; p < 4; p++) {
      cmul(zr, zi, w1r, w1i); sts32(bm + p * 16, pack2(zr, -zi));
      cmul(yr, yi, w2r, w2i); sts32(bm + 128 + p * 16, pack2(yr, -yi));
    }
    csq(w2r, w2i);
    sts32(bm + 128 + 64, pack2(xr, -xi));
    { float ur = xr, ui = xi; cmul(ur, ui, w2r, w2i); sts32(bm + 128 + 80, pack2(ur, -ui)); }
    cmul(xr, xi, Wr, Wi);
    sts32(bm + 128 + 96, pack2(xr, -xi));
    { float ur = xr, ui = xi; cmul(ur, ui, w2r, w2i); sts32(bm + 128 + 112, pack2(ur, -ui)); }
#pragma unroll
    for (int p = 4; p < 8; p++) {
      cmul(zr, zi, w1r, w1i); sts32(bm + p * 16, pack2(zr, -zi));
      cmul(xr, xi, Wr, Wi); sts32(bm + 256 + (p - 4) * 16, pack2(xr, -xi));
    }
    cmul(xr, xi, Wr, Wi);
    sts32(bm + 256 + 64, pack2(xr, -xi));
  }
  __syncwarp();
  if (ts >= 0 && tid == 0) TSTAMP(ts);
  if (dnext >= 0) raw = load_raw(P, dnext, tid);
  float d[2][3][4];
#pragma unroll
  for (int q = 0; q < 24; q++) (&d[0][0][0])[q] = 0.f;
  {
    const uint32_t bma = kt + w * 8 * BMP + ((lane >> 3) & 1) * BMP + (lane >> 4) * 128 + (lane & 7) * 16;
#pragma unroll
    for (int ks = 0; ks < 4; ks++) {
      uint32_t A[2][4], B[6];
      ldsm4(bma + 2 * ks * BMP, B[0], B[1], B[2], B[3]);
      ldsm2(bma + 2 * ks * BMP + 256 - (lane >> 4) * 128, B[4], B[5]);
#pragma unroll
      for (int m = 0; m < 2; m++) {
        const uint4 pr = lds128(ap + (32 * w + 8 * ks + 4 * m + t) * 16);
        const float Wr = __uint_as_float(pr.z), Wi = __uint_as_float(pr.w);
        float zr, zi;
        polar(__uint_as_float(pr.x), __uint_as_float(pr.y), pf, zr, zi);
        A[0][2 * m] = pack2(zr, zi);
        cmul(zr, zi, Wr, Wi); A[0][2 * m + 1] = pack2(zr, zi);
        cmul(zr, zi, Wr, Wi); A[1][2 * m] = pack2(zr, zi);
        cmul(zr, zi, Wr, Wi); A[1][2 * m + 1] = pack2(zr, zi);
      }
#pragma unroll
      for (int mt = 0; mt < 2; mt++)
#pragma unroll
        for (int n = 0; n < 3; n++) mma16816(d[mt][n], A[mt][0], A[mt][1], A[mt][2], A[mt][3], B[2 * n], B[2 * n + 1]);
    }
  }
  __syncwarp();
  if (ts >= 0 && tid == 0) TSTAMP(ts + 1);
  {
    const uint32_t ra = kt + w * 8 * BMP + (g * 24 + 2 * t) * 4;
#pragma unroll
    for (int mt = 0; mt < 2; mt++)
#pragma unroll
      for (int n = 0; n < 3; n++) {
        sts64f(ra + (16 * mt * 24 + 8 * n) * 4, d[mt][n][0], d[mt][n][1]);
        sts64f(ra + ((16 * mt + 8) * 24 + 8 * n) * 4, d[mt][n][2], d[mt][n][3]);
      }
  }
  bar_sync(barid, 128);
  if (ts >= 0 && tid == 0) TSTAMP(ts + 2);
  {
    const uint32_t ra = kt + (rr * 24 + c6) * 4;
    float2 v[3][4];
#pragma unroll
    for (int pp = 0; pp < 3; pp++)
#pragma unroll
      for (int q = 0; q < 4; q++) v[pp][q] = lds64f(ra + pp * 8 + q * 8 * BMP);
    constexpr uint32_t T[3][4] = {{0 | 8 << 10 | 1 << 14, 6 | 8 << 10 | 1 << 14, 384 | 2 << 10 | 1 << 14, 576 | 1 << 10 | 32 << 14},
                                  {2 | 8 << 10 | 1 << 14, 256 | 4 << 10 | 1 << 14, 448 | 2 << 10 | 1 << 14, 642},
                                  {4 | 8 << 10 | 1 << 14, 258 | 4 << 10 | 1 << 14, 512 | 1 << 10 | 32 << 14, 642}};
#pragma unroll
    for (int pp = 0; pp < 3; pp++) {
      const uint32_t e0 = (tid & 1) ? T[pp][1] : T[pp][0], e1 = (tid & 1) ? T[pp][3] : T[pp][2], e = (tid & 2) ? e1 : e0;
      uint32_t i0 = (e & 1023) + ((e >> 10) & 15) * rr;
      const uint32_t i1 = i0 + (e >> 14);
      if (pp == 1 && tid == 3) i0 = 640;
      float s0 = (v[pp][0].x + v[pp][1].x) + (v[pp][2].x + v[pp][3].x);
      const float s1 = (v[pp][0].y + v[pp][1].y) + (v[pp][2].y + v[pp][3].y);
      if (pp == 0 && tid == 0) s0 += dsk;
      const uint32_t pv = pack2(s0, s1);
      sts16(kc + i0 * 2, pv & 0xffffu); sts16(kc + i1 * 2, pv >> 16);
    }
  }
  bar_sync(barid, 128);
}

__device__ __forceinline__ void pexp(uint32_t kc, uint32_t pb) {
  const int tid = threadIdx.x & 127;
  if (tid < 64) {
    const uint32_t ab = lds32(kc + (512 + 2 * tid) * 2), cc = lds16(kc + (514 + 2 * tid) * 2);
    const uint32_t AA = __byte_perm(ab, 0, 0x1010), BB = __byte_perm(ab, 0, 0x3232), BA = __byte_perm(ab, 0, 0x1032);
    const uint32_t CB = __byte_perm(cc, ab, 0x7610), CC = __byte_perm(cc, 0, 0x1010);
    const uint32_t o = pb + (32 + 1024 + 16 * tid) * 4;
#pragma unroll
    for (int e = 0; e < 4; e++) {
      const int pc = (e + (tid >> 1)) & 3;
      const uint32_t x0 = pc == 3 ? CB : (pc == 2 ? BB : AA), x1 = pc == 0 ? AA : (pc == 1 ? BA : (pc == 2 ? BB : CC));
      const uint32_t x2 = pc == 0 ? AA : (pc == 3 ? CC : BB);
      sts128(o + pc * 16, x0, x1, x2, x2);
    }
  } else {
    const int q = tid - 64;
    {
      const uint32_t ab = lds32(kc + (384 + 2 * q) * 2), cc = lds16(kc + (386 + 2 * q) * 2);
      const uint32_t AA = __byte_perm(ab, 0, 0x1010), BB = __byte_perm(ab, 0, 0x3232), BA = __byte_perm(ab, 0, 0x1032);
      const uint32_t CB = __byte_perm(cc, ab, 0x7610), CC = __byte_perm(cc, 0, 0x1010);
      const uint32_t o = pb + (32 + 512 + 8 * q) * 4;
      const bool sw = (q >> 2) & 1;
      sts128(o + (sw ? 16 : 0), sw ? BB : AA, sw ? BB : AA, sw ? CB : AA, sw ? CC : BA);
      sts128(o + (sw ? 0 : 16), sw ? AA : BB, sw ? AA : BB, sw ? AA : CB, sw ? BA : CC);
    }
    {
      const uint32_t ab = lds32(kc + (256 + 2 * q) * 2), cc = lds16(kc + (258 + 2 * q) * 2);
      const uint32_t pv = q == 0 ? lds16(kc + 255 * 2) : (ab & 0xffffu);
      sts128(pb + (32 + 256 + 4 * q) * 4, __byte_perm(ab, pv, 0x5410), __byte_perm(ab, 0, 0x1010), __byte_perm(ab, 0, 0x1032), __byte_perm(cc, ab, 0x7610));
    }
#pragma unroll
    for (int e = 0; e < 2; e++) {
      const int qq = q + 64 * e;
      if (qq < 72) {
        uint32_t a = 0, bq = 0, pz = 0;
        if (qq >= 8) { const uint32_t s = kc + (4 * qq - 32) * 2; a = lds32(s); bq = lds32(s + 4); pz = lds32(s - 4); }
        sts128(pb + qq * 16, __byte_perm(a, pz, 0x7610), __byte_perm(a, 0, 0x1032), __byte_perm(bq, a, 0x7610), __byte_perm(bq, 0, 0x1032));
      }
    }
  }
}

__device__ __forceinline__ void kgen_role(uint32_t sb, const Params& P, Raw raw, long long t_start) {
  const int tid = threadIdx.x & 127, lane = tid & 31;
  const int b = blockIdx.x;
  const uint32_t bar = sb + OFF_BAR;
#pragma unroll 1
  for (int ch = 0; ch < 5; ch++) {
    kgen_channel(sb + OFF_KT, sb + OFF_KC + ch * KCB, 4, P, raw, 5 * b + ch, ch < 4 ? 5 * b + ch + 1 : -1, sb, t_start, ch == 1 ? 53 : (ch == 2 ? 59 : -1));
    if (tid == 0) TSTAMP(32 + ch);
    if (ch == 0) bar_sync(6, 160);
    mbar_wait(bar + (B_PEMPTY + (ch & 1)) * 8, (ch >> 1) & 1);
    pexp(sb + OFF_KC + ch * KCB + 16, sb + OFF_P + (ch & 1) * 8320);
    __syncwarp();
    if (lane == 0) mbar_arrive(bar + (B_PFULL + (ch & 1)) * 8);
    if (tid == 0) TSTAMP(40 + ch);
  }
  fence_async();
  bar_sync(4, 128);
  if (tid == 0) TSTAMP(16);
}

template <int G> struct CG { static constexpr int k0 = 2 * G, nk = 2, NG = 16; };
template <int G> __device__ __forceinline__ void conv_load(uint32_t* v, uint32_t paddr) {
#pragma unroll
  for (int kk = 0; kk < CG<G>::nk; kk++) {
    const uint32_t a = paddr + 256 * (CG<G>::k0 + kk);
    v[4 * kk] = lds32(a); v[4 * kk + 1] = lds32(a + 64); v[4 * kk + 2] = lds32(a - 32); v[4 * kk + 3] = lds32(a + 32);
  }
}
template <int G> __device__ __forceinline__ void conv_run(float (&acc)[4][16], uint32_t (&v)[3][8], uint32_t paddr, uint32_t ulo) {
  if constexpr (G + 1 < CG<G>::NG) conv_load<G + 1>(v[(G + 1) % 3], paddr);
  wg_fence();
#pragma unroll
  for (int kk = 0; kk < CG<G>::nk; kk++) {
    const int kap = CG<G>::k0 + kk;
#pragma unroll
    for (int q = kap / 8; q < 4; q++)
      wgmma_rs<32>(acc[q], v[G % 3][4 * kk], v[G % 3][4 * kk + 1], v[G % 3][4 * kk + 2], v[G % 3][4 * kk + 3],
                   desc_mk(ulo + (32 + 32 * q - 4 * kap), 128, 0), kap != 0);
  }
  wg_commit();
  if constexpr (G + 1 < CG<G>::NG) { wg_wait<1>(); conv_run<G + 1>(acc, v, paddr, ulo); } else { wg_wait<0>(); }
}

__device__ __forceinline__ void conv_role(uint32_t sb, const CUtensorMap* tmUS, const CUtensorMap* tmUL, unsigned epoch, long long t_start) {
  const int tid = threadIdx.x & 127, lane = tid & 31, w = tid >> 5, g = lane >> 2, t = lane & 3;
  const int b = blockIdx.x, i = b >> 3, j = b & 7;
  const uint32_t bar = sb + OFF_BAR;
  sts128(sb + OFF_UT + (tid >> 5) * UPL + (tid & 31) * 16, 0, 0, 0, 0);
  if (tid < 30) reinterpret_cast<float4*>(g_kv[(epoch + 1) & 1])[b * 30 + tid] = make_float4(0.f, 0.f, 0.f, 0.f);
  if (tid == 0) mbar_arrive_n(bar + (B_PEMPTY + 0) * 8, 4);
  mbar_wait(bar + B_XS * 8, 0);
  if (tid == 0) TSTAMP(26);
#pragma unroll 2
  for (int db = 0; db < 10; db++) {
    uint32_t r0, r1, r2, r3;
    const int r = lane & 7, nn = 4 * (w >> 1) + (lane >> 3);
    ldsm4t(sb + OFF_XS + (16 * nn + 8 * (w & 1) + r) * 160 + db * 16, r0, r1, r2, r3);
    stsm4(sb + ((w & 1) ? OFF_XT1 : OFF_XT0) + (8 * db + r) * 128 + ((nn ^ r) << 4), r0, r1, r2, r3);
  }
  {
    float s = 0.f;
#pragma unroll
    for (int q = 0; q < 10; q++) {
      const uint4 xv = lds128(sb + OFF_XS + tid * 160 + q * 16), gv = lds128(sb + OFF_GW + q * 16);
      const uint32_t p0 = hmul2rn(xv.x, gv.x), p1 = hmul2rn(xv.y, gv.y), p2 = hmul2rn(xv.z, gv.z), p3 = hmul2rn(xv.w, gv.w);
      s += (bf_lo(p0) + bf_hi(p0)) + (bf_lo(p1) + bf_hi(p1)) + (bf_lo(p2) + bf_hi(p2)) + (bf_lo(p3) + bf_hi(p3));
    }
    sts32f(sb + OFF_GP + tid * 4, s);
  }
  fence_async();
  bar_sync(5, 128);
  auto load_u = [&](int ch) {
    const uint32_t fb = bar + (B_UT + (ch & 1)) * 8;
    mbar_expect_tx(fb, 4096);
#pragma unroll
    for (int h = 0; h < 2; h++) tma4d(sb + OFF_UT + (ch & 1) * 5120 + h * UPL + 512, tmUL, 0, h, 0, 5 * b + ch, fb);
  };
  if (tid == 0) {
    tma2d_store(tmUS, sb + OFF_XT0, 128 * i, 80 * j);
    tma2d_store(tmUS, sb + OFF_XT1, 128 * i + 64, 80 * j);
    bulk_store(&g_gp[(i * 8 + j) * 128], sb + OFF_GP, 512);
    bulk_commit();
    mbar_arrive(bar + B_XD * 8);
    TSTAMP(27);
    bulk_wait_all();
    fence_async_g();
    red_relaxed(&g_cnt[(0 + j) * 32]);
    red_relaxed(&g_cnt[(16 + i) * 32]);
    mbar_arrive_n(bar + (B_PEMPTY + 1) * 8, 4);
    TSTAMP(28);
    poll_ge(&g_cnt[(0 + (b >> 4)) * 32], (epoch + 1) * 16);
    fence_async_g();
    load_u(0); load_u(1);
    TSTAMP(17);
  }
  __syncwarp();
  const bool lower = w < 2;
  const int p = w & 1;
#pragma unroll 1
  for (int ch = 0; ch < 5; ch++) {
    mbar_wait(bar + (B_PFULL + (ch & 1)) * 8, (ch >> 1) & 1);
    mbar_wait(bar + (B_UT + (ch & 1)) * 8, (ch >> 1) & 1);
    if (tid == 0) TSTAMP(24 + 0 * ch + (ch == 0 ? 6 : 7));
    float acc[4][16];
    const uint32_t pb = sb + OFF_P + (ch & 1) * 8320;
    {
      uint32_t v[3][8];
      const uint32_t paddr = pb + (32 + 8 * p + 32 * (w >> 1) + g - 2 * t) * 4;
      conv_load<0>(v[0], paddr);
      conv_run<0>(acc, v, paddr, desc_lo(sb + OFF_UT + (ch & 1) * 5120, UPL));
    }
    if (tid == 0) { TSTAMP(48 + ch); bulk_wait_read(); }
    float F[16][2];
    {
      float prev = 0.f;
#pragma unroll
      for (int nb = 0; nb < 16; nb++) {
        const float* a = &acc[nb >> 2][4 * (nb & 3)];
        const float r = __shfl_sync(0xffffffffu, a[3], (lane & ~3) | ((t + 3) & 3));
        F[nb][0] = a[0] + (t > 0 ? r : prev); F[nb][1] = a[1] + a[2];
        prev = r;
      }
    }
    bar_sync(5, 128);
    if (tid == 0 && ch + 2 < 5) load_u(ch + 2);
    {
      const uint32_t xs = pb + (2 * p + (lower ? 0 : 1)) * 2048 + g * 256 + 8 * t;
#pragma unroll
      for (int k = 0; k < 8; k++) sts64f(xs + ((k ^ (g & 3)) << 5), lower ? F[8 + k][0] : F[k][0], lower ? F[8 + k][1] : F[k][1]);
    }
    bar_sync(5, 128);
    {
      const uint32_t xr = pb + (2 * p + (lower ? 1 : 0)) * 2048 + g * 256;
      uint32_t pk[9];
#pragma unroll
      for (int k = 0; k < 9; k++) {
        const int col = 8 * k + 2 * t + (lower ? -2 : 2);
        float2 o = make_float2(0.f, 0.f);
        if ((unsigned)col < 64u) o = lds64f(xr + ((col ^ ((g & 3) << 3)) << 2));
        const float f0 = k == 8 ? F[8][0] : (lower ? F[k][0] : F[8 + k][0]), f1 = k == 8 ? F[8][1] : (lower ? F[k][1] : F[8 + k][1]);
        pk[k] = pack2(f0 + o.x, f1 + o.y);
      }
      __syncwarp();
      if (lane == 0) mbar_arrive(bar + (B_PEMPTY + (ch & 1)) * 8);
      const int mi = lane >> 3, r = lane & 7;
      const uint32_t dummy = sb + OFF_GP + r * 16;
#pragma unroll
      for (int hf = 0; hf < 2; hf++) {
        const int n = 8 * (4 * hf + mi) + r + (lower ? 0 : 66);
        stsm4t(n < 128 ? sb + OFF_YST + 32 * n + 16 * p : dummy, pk[4 * hf], pk[4 * hf + 1], pk[4 * hf + 2], pk[4 * hf + 3]);
      }
      if (lower) stsm1t(r < 2 ? sb + OFF_YST + 32 * (64 + r) + 16 * p : dummy, pk[8]);
    }
    fence_async();
    bar_sync(5, 128);
    if (tid == 0) { bulk_store((uint8_t*)g_aT + (size_t)(5 * b + ch) * 4096, sb + OFF_YST, 4096); bulk_commit(); TSTAMP(18 + ch); }
    __syncwarp();
  }
  if (tid == 0) { bulk_wait_all(); fence_async_g(); red_relaxed(&g_cnt[(32 + (b >> 4)) * 32]); TSTAMP(29); }
}

__device__ __forceinline__ void g1_load(uint32_t sb, const CUtensorMap* tmX, const CUtensorMap* tmW128, const CUtensorMap* tmW32, int kb) {
  const int i = blockIdx.x >> 3, j = blockIdx.x & 7, s = kb % NST;
  const uint32_t st = sb + s * STG, fb = sb + OFF_BAR + (B_FULL + s) * 8;
  mbar_expect_tx(fb, STG);
  tma3d(st + 16384, tmW128, 80 * j, kb * 64, 0, fb);
  tma2d(st, tmX, kb * 64, i * 128, fb);
  tma3d(st + 16384 + 24576, tmW32, 80 * j + 64, kb * 64, 0, fb);
}

__device__ __forceinline__ void gemm_role(uint32_t sb, const CUtensorMap* tmX, const CUtensorMap* tmW128, const CUtensorMap* tmW32, const CUtensorMap* tmWO,
                                          const CUtensorMap* tmOst, const CUtensorMap* tmOut, int wg, unsigned epoch, long long t_start) {
  const int tid = threadIdx.x & 127, lane = tid & 31, w = tid >> 5, g = lane >> 2, t = lane & 3;
  const int b = blockIdx.x, i = b >> 3, j = b & 7;
  const uint32_t bar = sb + OFF_BAR;
  uint32_t pq[10][2];
  {
    float d[120];
#pragma unroll
    for (int q = 0; q < 120; q++) d[q] = 0.f;
#pragma unroll 1
    for (int kb = 0; kb < 10; kb++) {
      const int s = kb % NST;
      mbar_wait(bar + (B_FULL + s) * 8, (kb / NST) & 1);
      const uint32_t st = sb + s * STG;
      const uint32_t alo = desc_lo(st + wg * 8192, 16), blo = desc_lo(st + 16384, 8192), clo = desc_lo(st + 16384 + 24576, 2048);
#pragma unroll
      for (int hf = 0; hf < G1B; hf++) {
        wg_fence();
#pragma unroll
        for (int ks = hf * (4 / G1B); ks < (hf + 1) * (4 / G1B); ks++) {
          const uint64_t da = desc_mk(alo + ks * 2, 1024, 1);
          wgmma_g1a(d, da, desc_mk(blo + ks * 128, 1024, 1), (kb | ks) != 0);
          wgmma_g1b(d, da, desc_mk(clo + ks * 32, 256, 3), (kb | ks) != 0);
        }
        wg_commit();
        wg_wait<1>();
        if (hf == 0 && kb > 0 && tid == 0 && (atom_inc_smem(sb + OFF_CNT + ((kb - 1) % NST) * 4) & 1)) {
          if (kb + 2 < 10) {
            g1_load(sb, tmX, tmW128, tmW32, kb + 2);
          } else {
            mbar_wait(bar + B_XD * 8, 0);
            const int p0 = kb == 8 ? 0 : 4, p1 = kb == 8 ? 4 : 10;
            mbar_expect_tx(bar + B_WO * 8, (p1 - p0) * 10240);
#pragma unroll 1
            for (int p = p0; p < p1; p++) tma3d(sb + OFF_WO + p * 10240, tmWO, 0, p * 64, 5 * j, bar + B_WO * 8);
          }
        }
      }
    }
    wg_wait<0>();
    if (tid == 0) {
      TSTAMP(wg);
    }
    __syncwarp();
    mbar_wait(bar + B_XD * 8, 0);
    bar_sync(1, 256);
    if (tid == 0 && wg == 0) TSTAMP(23);
    const uint32_t rowa = (uint32_t)(wg * 64 + 16 * w + g) * 208;
#pragma unroll
    for (int nb = 0; nb < 10; nb++) {
      const int c = 8 * nb + 2 * t;
      const int cc = c + 4 * ((c >= 20) + (c >= 40) + (c >= 60));
      sts32(sb + OFF_PK + rowa + cc * 2, phi2(d[40 + 4 * nb], d[40 + 4 * nb + 1]));
      sts32(sb + OFF_PK + rowa + 8 * 208 + cc * 2, phi2(d[40 + 4 * nb + 2], d[40 + 4 * nb + 3]));
      sts32(sb + OFF_V + rowa + cc * 2, pack2(d[80 + 4 * nb], d[80 + 4 * nb + 1]));
      sts32(sb + OFF_V + rowa + 8 * 208 + cc * 2, pack2(d[80 + 4 * nb + 2], d[80 + 4 * nb + 3]));
    }
    bar_sync(2 + wg, 128);
    if (tid == 0 && wg == 0) TSTAMP(24);
    {
      float acc[2][3][4];
#pragma unroll
      for (int m = 0; m < 2; m++)
#pragma unroll
        for (int n = 0; n < 3; n++) { acc[m][n][0] = acc[m][n][1] = acc[m][n][2] = acc[m][n][3] = 0.f; }
      const int mi = lane >> 3, r = lane & 7;
#pragma unroll
      for (int ks = 0; ks < 4; ks++) {
        const int s0 = wg * 64 + 16 * ks;
        uint32_t A[2][4], B[3][2];
#pragma unroll
        for (int m = 0; m < 2; m++)
          ldsm4t(sb + OFF_PK + (s0 + r + 8 * (mi >> 1)) * 208 + (24 * w + 16 * m + 8 * (mi & 1)) * 2, A[m][0], A[m][1], A[m][2], A[m][3]);
        ldsm4t(sb + OFF_V + (s0 + r + 8 * (mi & 1)) * 208 + (24 * w + 8 * (mi >> 1)) * 2, B[0][0], B[0][1], B[1][0], B[1][1]);
        ldsm2t(sb + OFF_V + (s0 + r + 8 * (mi & 1)) * 208 + (24 * w + 16) * 2, B[2][0], B[2][1]);
        if (g >= 4) { B[2][0] = B[2][1] = (g == 4) ? 0x3F803F80u : 0u; }
#pragma unroll
        for (int m = 0; m < 2; m++)
#pragma unroll
          for (int n = 0; n < 3; n++) mma16816(acc[m][n], A[m][0], A[m][1], A[m][2], A[m][3], B[n][0], B[n][1]);
      }
      bar_sync(2 + wg, 128);
      const uint32_t kr = sb + OFF_PK + wg * 13312 + w * 1920;
#pragma unroll
      for (int n = 0; n < 3; n++) {
        sts64f(kr + (g * 24 + 8 * n + 2 * t) * 4, acc[0][n][0], acc[0][n][1]);
        sts64f(kr + ((g + 8) * 24 + 8 * n + 2 * t) * 4, acc[0][n][2], acc[0][n][3]);
        if (g < 4) sts64f(kr + ((g + 16) * 24 + 8 * n + 2 * t) * 4, acc[1][n][0], acc[1][n][1]);
      }
    }
    if (tid == 0 && wg == 0) TSTAMP(25);
    fence_async();
    bar_sync(2 + wg, 128);
    if (tid == 0 && wg == 0) TSTAMP(56);
    if (tid == 0) {
      bulk_reduce_f32(&g_kv[epoch & 1][j * 1920], sb + OFF_PK + wg * 13312, 7680);
      bulk_commit(); bulk_wait_all();
      if (wg == 0) TSTAMP(57);
      fence_async_g();
      if (wg == 0) TSTAMP(58);
      red_relaxed(&g_cnt[(8 + j) * 32]);
      TSTAMP(2 + wg);
    }
    __syncwarp();
#pragma unroll
    for (int q = 0; q < 40; q++) asm volatile("" : "+f"(d[q]) :: "memory");
#pragma unroll
    for (int nb = 0; nb < 10; nb++) { pq[nb][0] = phi2(d[4 * nb], d[4 * nb + 1]); pq[nb][1] = phi2(d[4 * nb + 2], d[4 * nb + 3]); }
  }
  for (int q = wg * 128 + tid; q < 968; q += 256) sts128(sb + OFF_BT + q * 16, 0, 0, 0, 0);
  if (wg == 0 && tid == 0) poll_ge(&g_cnt[(8 + j) * 32], (epoch + 1) * 32);
  __syncwarp();
  bar_sync(1, 256);
  if (tid == 0) TSTAMP(4 + wg);
  for (int q = wg * 128 + tid; q < 480; q += 256) {
    const float4 v = __ldcg(reinterpret_cast<const float4*>(&g_kv[epoch & 1][j * 1920]) + q);
    const int h = q / 120, rem = q - 120 * h, dd = rem / 6, e4 = rem - 6 * dd;
    const uint32_t col = sb + OFF_BT + (20 * h + dd) * 2;
    if (e4 < 5) {
      const uint32_t a = col + (20 * h + 4 * e4) * 176;
      sts16(a, __bfloat16_as_ushort(__float2bfloat16_rn(v.x))); sts16(a + 176, __bfloat16_as_ushort(__float2bfloat16_rn(v.y)));
      sts16(a + 352, __bfloat16_as_ushort(__float2bfloat16_rn(v.z))); sts16(a + 528, __bfloat16_as_ushort(__float2bfloat16_rn(v.w)));
    } else {
      sts16(col + (80 + h) * 176, __bfloat16_as_ushort(__float2bfloat16_rn(v.x)));
    }
  }
  bar_sync(1, 256);
  {
    float num[10][4], den[4];
#pragma unroll
    for (int n = 0; n < 10; n++) { num[n][0] = num[n][1] = num[n][2] = num[n][3] = 0.f; }
    den[0] = den[1] = den[2] = den[3] = 0.f;
    const uint32_t bt = sb + OFF_BT + g * 176 + t * 4;
#pragma unroll
    for (int ks = 0; ks < 5; ks++) {
      const uint32_t a0 = pq[2 * ks][0], a1 = pq[2 * ks][1], a2 = pq[2 * ks + 1][0], a3 = pq[2 * ks + 1][1];
#pragma unroll
      for (int n = 0; n < 10; n++) {
        const int h0 = (8 * n) / 20, h1 = (8 * n + 7) / 20;
        if (16 * ks + 15 >= 20 * h0 && 16 * ks < 20 * h1 + 20)
          mma16816(num[n], a0, a1, a2, a3, lds32(bt + n * 8 * 176 + ks * 32), lds32(bt + n * 8 * 176 + ks * 32 + 16));
      }
      mma16816(den, a0, a1, a2, a3, lds32(bt + 80 * 176 + ks * 32), lds32(bt + 80 * 176 + ks * 32 + 16));
    }
    float rd[4];
#pragma unroll
    for (int q = 0; q < 4; q++) rd[q] = __frcp_rn(bfr(bfr(den[q]) + 1e-6f));
    float rh[4][2];
#pragma unroll
    for (int h = 0; h < 4; h++) {
      rh[h][0] = __shfl_sync(0xffffffffu, rd[h & 1], (lane & ~3) | (h >> 1));
      rh[h][1] = __shfl_sync(0xffffffffu, rd[2 + (h & 1)], (lane & ~3) | (h >> 1));
    }
    const uint32_t oa = sb + OFF_OST + (uint32_t)(wg * 64 + 16 * w + g) * 160 + t * 4;
#pragma unroll
    for (int n = 0; n < 10; n++) {
      const int h0 = (8 * n) / 20, h1 = (8 * n + 7) / 20;
      float r0 = rh[h0][0], r1 = rh[h0][1];
      if (h1 != h0 && t >= 2) { r0 = rh[h1][0]; r1 = rh[h1][1]; }
      sts32(oa + n * 16, pack2(bfr(num[n][0]) * r0, bfr(num[n][1]) * r0));
      sts32(oa + 8 * 160 + n * 16, pack2(bfr(num[n][2]) * r1, bfr(num[n][3]) * r1));
    }
  }
  fence_async();
  bar_sync(2 + wg, 128);
  if (tid == 0) {
    mbar_arrive(bar + B_P2 * 8);
    tma2d_store(tmOst, sb + OFF_OST + wg * 64 * 160, 80 * j, 128 * i + 64 * wg);
    bulk_commit(); bulk_wait_all(); fence_async_g();
    red_relaxed(&g_cnt[(16 + i) * 32]);
    TSTAMP(6 + wg);
  }
  __syncwarp();
  float d[40];
#pragma unroll
  for (int q = 0; q < 40; q++) d[q] = 0.f;
  float gpv[16];
#pragma unroll
  for (int q = 0; q < 16; q++) gpv[q] = 0.f;
  mbar_wait(bar + B_WO * 8, 0);
#pragma unroll 1
  for (int kb = 0; kb < 10; kb++) {
    const int s = kb & 3;
    mbar_wait(bar + (B_OFULL + s) * 8, (kb >> 2) & 1);
    if (kb == 0 && tid == 0) TSTAMP(8 + wg);
    const uint32_t alo = desc_lo(sb + oring(s) + wg * 8192, 16), blo = desc_lo(sb + OFF_WO + kb * 10240, 2048);
    wg_fence();
#pragma unroll
    for (int ks = 0; ks < 4; ks++) wgmma_g2(d, desc_mk(alo + ks * 2, 1024, 1), desc_mk(blo + ks * 32, 256, 3), (kb | ks) != 0);
    wg_commit();
    if (kb == 1) {
      const float* gp = &g_gp[i * 8 * 128 + wg * 64 + 16 * w + g];
#pragma unroll
      for (int q = 0; q < 16; q++) asm volatile("ld.global.cg.f32 %0, [%1];" : "=f"(gpv[q]) : "l"(gp + (q & 7) * 128 + (q >> 3) * 8) : "memory");
    }
    wg_wait<1>();
    if (kb > 0 && tid == 0) mbar_arrive(bar + (B_OEMPTY + ((kb - 1) & 3)) * 8);
  }
  uint32_t g2[2], og2[2];
#pragma unroll
  for (int h = 0; h < 2; h++) {
    float s = 0.f;
#pragma unroll
    for (int q = 0; q < 8; q++) s += gpv[h * 8 + q];
    s = bfr(s);
    float gg = bfr(1.f / (1.f + __expf(-s)));
    float og = bfr(1.f - gg);
    g2[h] = pack2(gg, gg); og2[h] = pack2(og, og);
  }
  wg_wait<0>();
  if (tid == 0) TSTAMP(10 + wg);
  bar_sync(1, 256);
  mbar_wait(bar + B_AT * 8, 0);
  if (tid == 0) TSTAMP(12 + wg);
  {
    const int mi = lane >> 3, r = lane & 7;
    const uint32_t oa = sb + OFF_OUT + (uint32_t)(wg * 64 + 16 * w + g) * 160 + t * 4;
#pragma unroll
    for (int n = 0; n < 10; n += 2) {
      uint32_t a0, a1, a2, a3;
      const int chn = 8 * (n + (mi >> 1)) + r, chunk = 2 * w + (mi & 1);
      ldsm4t(sb + OFF_AT + wg * 10240 + chn * 128 + ((chunk ^ (chn & 7)) << 4), a0, a1, a2, a3);
      sts32(oa + n * 16, hadd2rn(hmul2rn(g2[0], a0), hmul2rn(og2[0], pack2(d[4 * n], d[4 * n + 1]))));
      sts32(oa + 8 * 160 + n * 16, hadd2rn(hmul2rn(g2[1], a1), hmul2rn(og2[1], pack2(d[4 * n + 2], d[4 * n + 3]))));
      sts32(oa + n * 16 + 16, hadd2rn(hmul2rn(g2[0], a2), hmul2rn(og2[0], pack2(d[4 * n + 4], d[4 * n + 5]))));
      sts32(oa + 8 * 160 + n * 16 + 16, hadd2rn(hmul2rn(g2[1], a3), hmul2rn(og2[1], pack2(d[4 * n + 6], d[4 * n + 7]))));
    }
  }
  fence_async();
  bar_sync(2 + wg, 128);
  if (tid == 0) {
    tma2d_store(tmOut, sb + OFF_OUT + wg * 64 * 160, 80 * j, 128 * i + 64 * wg);
    bulk_commit(); bulk_wait_all();
    TSTAMP(14 + wg);
  }
}

__global__ void __launch_bounds__(512, 1)
fused_kernel(const __grid_constant__ CUtensorMap tmX, const __grid_constant__ CUtensorMap tmW128, const __grid_constant__ CUtensorMap tmW32,
             const __grid_constant__ CUtensorMap tmXS, const __grid_constant__ CUtensorMap tmWO, const __grid_constant__ CUtensorMap tmOld,
             const __grid_constant__ CUtensorMap tmOst, const __grid_constant__ CUtensorMap tmAT, const __grid_constant__ CUtensorMap tmOut,
             const __grid_constant__ CUtensorMap tmUS, const __grid_constant__ CUtensorMap tmUL, const Params P) {
  extern __shared__ __align__(1024) uint8_t sm_raw[];
  const uint32_t sb = smem_u32(sm_raw);
  const uint32_t bar = sb + OFF_BAR;
  const long long t_start = 0;
  const int tid = threadIdx.x;
  const int warp = __shfl_sync(0xffffffffu, tid >> 5, 0);
  const int b = blockIdx.x, i = b >> 3, j = b & 7;
  Raw raw;
  if (warp >= 12) {
    asm volatile("setmaxnreg.dec.sync.aligned.u32 80;");
    raw = load_raw(P, 5 * b, tid & 127);
    kgen_role(sb, P, raw, t_start);
    const unsigned epoch = lds32(sb + OFF_CNT + 20);
    if (warp == 12) {
      const bool leader = elect();
      mbar_wait(bar + B_P2 * 8, 0);
      if (leader) {
        poll_ge(&g_cnt[(16 + i) * 32], (epoch + 1) * 24);
        fence_async_g();
        if (b == 0) g_epoch = epoch + 1;
      }
      __syncwarp();
#pragma unroll 1
      for (int kb = 0; kb < 10; kb++) {
        const int s = kb & 3;
        mbar_wait(bar + (B_OEMPTY + s) * 8, ((kb >> 2) & 1) ^ 1);
        if (leader) {
          mbar_expect_tx(bar + (B_OFULL + s) * 8, 16384);
          tma2d(sb + oring(s), &tmOld, kb * 64, i * 128, bar + (B_OFULL + s) * 8);
        }
        __syncwarp();
      }
    } else if (warp == 13) {
      mbar_wait(bar + B_P2 * 8, 0);
      if (elect()) {
        poll_ge(&g_cnt[(32 + j) * 32], (epoch + 1) * 16);
        fence_async_g();
        mbar_expect_tx(bar + B_AT * 8, 20480);
        tma2d(sb + OFF_AT, &tmAT, 128 * i, 80 * j, bar + B_AT * 8);
        tma2d(sb + OFF_AT + 10240, &tmAT, 128 * i + 64, 80 * j, bar + B_AT * 8);
      }
      __syncwarp();
    }
  } else {
    if (tid == 0) {
      if (sb & 1023) __trap();
      for (int s = 0; s < 3; s++) mbar_init(bar + (B_FULL + s) * 8, 1);
      mbar_init(bar + B_XS * 8, 1);
      fence_async();
      mbar_expect_tx(bar + B_XS * 8, 20480 + 160);
      tma2d(sb + OFF_XS, &tmXS, 80 * j, 128 * i, bar + B_XS * 8);
      bulk_load(sb + OFF_GW, P.gatew + 80 * j, 160, bar + B_XS * 8);
      for (int s = 0; s < 3; s++) g1_load(sb, &tmX, &tmW128, &tmW32, s);
    } else if (tid == 32) {
      for (int s = 0; s < 4; s++) { mbar_init(bar + (B_OFULL + s) * 8, 1); mbar_init(bar + (B_OEMPTY + s) * 8, 2); }
      mbar_init(bar + B_WO * 8, 2); mbar_init(bar + B_AT * 8, 1);
      for (int s = 0; s < 2; s++) { mbar_init(bar + (B_UT + s) * 8, 1); mbar_init(bar + (B_PFULL + s) * 8, 4); mbar_init(bar + (B_PEMPTY + s) * 8, 4); }
      mbar_init(bar + B_P2 * 8, 2); mbar_init(bar + B_XD * 8, 1);
      for (int s = 0; s < 5; s++) sts32(sb + OFF_CNT + s * 4, 0);
      asm volatile("fence.mbarrier_init.release.cluster;" ::: "memory");
      fence_async();
    } else if (tid == 96) {
      unsigned e;
      asm volatile("ld.relaxed.gpu.global.u32 %0, [%1];" : "=r"(e) : "l"(&g_epoch) : "memory");
      sts32(sb + OFF_CNT + 20, e);
    } else if (warp == 2 && (tid & 31) < 7) {
      const CUtensorMap* tm = &tmUS;
      const int q = tid & 31;
      tm = q == 1 ? &tmUL : tm; tm = q == 2 ? &tmOst : tm; tm = q == 3 ? &tmOld : tm; tm = q == 4 ? &tmWO : tm; tm = q == 5 ? &tmAT : tm; tm = q == 6 ? &tmOut : tm;
      asm volatile("prefetch.tensormap [%0];" ::"l"(tm) : "memory");
    }
    bar_sync(7, 384);
    if (warp == 1) asm volatile("bar.arrive 6, 160;" ::: "memory");
    const unsigned epoch = lds32(sb + OFF_CNT + 20);
    if (tid == 0) TSTAMP(38);
    if (warp < 8) {
      asm volatile("setmaxnreg.inc.sync.aligned.u32 152;");
      gemm_role(sb, &tmX, &tmW128, &tmW32, &tmWO, &tmOst, &tmOut, warp >> 2, epoch, t_start);
    } else {
      conv_role(sb, &tmUS, &tmUL, epoch, t_start);
    }
  }
}

typedef CUresult (*EncFn)(CUtensorMap*, CUtensorMapDataType, cuuint32_t, void*, const cuuint64_t*, const cuuint64_t*, const cuuint32_t*,
                          const cuuint32_t*, CUtensorMapInterleave, CUtensorMapSwizzle, CUtensorMapL2promotion, CUtensorMapFloatOOBfill);

struct Host {
  CUtensorMap tmX, tmW128, tmW32, tmXS, tmWO, tmOld, tmOst, tmAT, tmOut, tmUS, tmUL;
  Params P;
  const void* key[14];
  bool ready;
};

static void enc(EncFn f, CUtensorMap* m, const void* base, int rank, const cuuint64_t* gd, const cuuint64_t* gs, const cuuint32_t* bx, CUtensorMapSwizzle sw) {
  cuuint32_t es[5] = {1, 1, 1, 1, 1};
  f(m, CU_TENSOR_MAP_DATA_TYPE_BFLOAT16, rank, const_cast<void*>(base), gd, gs, bx, es, CU_TENSOR_MAP_INTERLEAVE_NONE, sw,
    CU_TENSOR_MAP_L2_PROMOTION_L2_128B, CU_TENSOR_MAP_FLOAT_OOB_FILL_NONE);
}

}

extern "C" void kernel_launch(void* const* d_in, const int* in_sizes, int n_in, void* d_out, int out_size) {
  using namespace gm;
  (void)in_sizes; (void)n_in; (void)out_size;
  static Host H;
  bool same = H.ready;
  for (int q = 0; q < 13 && same; q++) same = (H.key[q] == d_in[q]);
  same = same && H.key[13] == d_out;
  if (!same) {
    void* fn = nullptr; cudaDriverEntryPointQueryResult qr;
    cudaGetDriverEntryPoint("cuTensorMapEncodeTiled", &fn, cudaEnableDefault, &qr);
    EncFn f = (EncFn)fn;
    void *p_o = nullptr, *p_at = nullptr, *p_ut = nullptr;
    cudaGetSymbolAddress(&p_o, g_o); cudaGetSymbolAddress(&p_at, g_aT); cudaGetSymbolAddress(&p_ut, g_uT);
    const void *x = d_in[0], *wqkv = d_in[10], *wo = d_in[11];
    { cuuint64_t gd[2] = {640, 2048}, gs[1] = {1280}; cuuint32_t bx[2] = {64, 128}; enc(f, &H.tmX, x, 2, gd, gs, bx, CU_TENSOR_MAP_SWIZZLE_128B); enc(f, &H.tmOld, p_o, 2, gd, gs, bx, CU_TENSOR_MAP_SWIZZLE_128B); }
    { cuuint64_t gd[3] = {640, 640, 3}, gs[2] = {3840, 1280}; cuuint32_t bx[3] = {64, 64, 3}; enc(f, &H.tmW128, wqkv, 3, gd, gs, bx, CU_TENSOR_MAP_SWIZZLE_128B); }
    { cuuint64_t gd[3] = {640, 640, 3}, gs[2] = {3840, 1280}; cuuint32_t bx[3] = {16, 64, 3}; enc(f, &H.tmW32, wqkv, 3, gd, gs, bx, CU_TENSOR_MAP_SWIZZLE_32B); }
    { cuuint64_t gd[2] = {640, 2048}, gs[1] = {1280}; cuuint32_t bx[2] = {80, 128}; enc(f, &H.tmXS, x, 2, gd, gs, bx, CU_TENSOR_MAP_SWIZZLE_NONE); }
    { cuuint64_t gd[3] = {16, 640, 40}, gs[2] = {1280, 32}; cuuint32_t bx[3] = {16, 64, 5}; enc(f, &H.tmWO, wo, 3, gd, gs, bx, CU_TENSOR_MAP_SWIZZLE_32B); }
    { cuuint64_t gd[2] = {640, 2048}, gs[1] = {1280}; cuuint32_t bx[2] = {80, 64}; enc(f, &H.tmOst, p_o, 2, gd, gs, bx, CU_TENSOR_MAP_SWIZZLE_NONE); enc(f, &H.tmOut, d_out, 2, gd, gs, bx, CU_TENSOR_MAP_SWIZZLE_NONE); }
    { cuuint64_t gd[2] = {2048, 640}, gs[1] = {4096}; cuuint32_t bx[2] = {64, 80}; enc(f, &H.tmAT, p_at, 2, gd, gs, bx, CU_TENSOR_MAP_SWIZZLE_128B); }
    { cuuint64_t gd[2] = {2048, 640}, gs[1] = {4096}; cuuint32_t bx[2] = {64, 80}; enc(f, &H.tmUS, p_ut, 2, gd, gs, bx, CU_TENSOR_MAP_SWIZZLE_128B); }
    { cuuint64_t gd[4] = {64, 2, 16, 640}, gs[3] = {128, 256, 4096}; cuuint32_t bx[4] = {64, 1, 16, 1}; enc(f, &H.tmUL, p_ut, 4, gd, gs, bx, CU_TENSOR_MAP_SWIZZLE_NONE); }
    H.P.Are = (const __nv_bfloat16*)d_in[1]; H.P.Aim = (const __nv_bfloat16*)d_in[2];
    H.P.Bre = (const __nv_bfloat16*)d_in[3]; H.P.Bim = (const __nv_bfloat16*)d_in[4];
    H.P.Cre = (const __nv_bfloat16*)d_in[5]; H.P.Cim = (const __nv_bfloat16*)d_in[6];
    H.P.logdt = (const __nv_bfloat16*)d_in[7]; H.P.dskip = (const __nv_bfloat16*)d_in[8]; H.P.gatew = (const __nv_bfloat16*)d_in[12];
    for (int q = 0; q < 13; q++) H.key[q] = d_in[q];
    H.key[13] = d_out;
    cudaFuncSetAttribute(fused_kernel, cudaFuncAttributeMaxDynamicSharedMemorySize, SMEM_BYTES);
    H.ready = true;
  }
  fused_kernel<<<128, 512, SMEM_BYTES, cudaStreamPerThread>>>(H.tmX, H.tmW128, H.tmW32, H.tmXS, H.tmWO, H.tmOld, H.tmOst, H.tmAT, H.tmOut, H.tmUS, H.tmUL, H.P);
}
```
